```python
import torch

def _softmax(x, axis=-1):
    return torch.softmax(x, dim=axis)
def _gelu(x):
    return torch.nn.functional.gelu(x, approximate="tanh")
def _silu(x):
    return torch.nn.functional.silu(x)
def _sigmoid(x):
    return torch.sigmoid(x)
def _layernorm(x, axis=-1, eps=1e-5):
    m = x.mean(dim=axis, keepdim=True)
    v = x.var(dim=axis, keepdim=True, unbiased=False)
    return (x - m) / torch.sqrt(v + eps)
def _scatter_add(tgt, idx, src, axis=0):
    return tgt.clone().index_add_(axis, idx, src)
def _segment_sum(src, seg, n):
    out = torch.zeros((n,) + src.shape[1:], dtype=src.dtype)
    return out.index_add_(0, seg, src)
def _pad(x, pw):
    flat = tuple(v for pair in reversed(pw) for v in pair)
    return torch.nn.functional.pad(x, flat)

kernel_name = 'gated_mix__linear_attn_block__linear_attn_block__prompt'

def setup_inputs():

    _w = (lambda a: (lambda t: t.to(torch.bfloat16) if t.is_floating_point() else t)(torch.as_tensor(a)))
    def _A_setup():
        B, S, D = 1, 2048, 512
        return {
            "x": _w((lambda *s: torch.randn(*s, dtype=torch.bfloat16) * 0.05)(B, S, D)),
            "wqkv": _w((lambda *s: torch.randn(*s, dtype=torch.bfloat16) * 0.8)(D, 3 * D)),
            "wo": _w((lambda *s: torch.randn(*s, dtype=torch.bfloat16) * 0.05)(D, D)),
        }
    _A_in = _A_setup()

    def _B_setup():
        B, S, D = 1, 2048, 512
        return {
            "x": _w((lambda *s: torch.randn(*s, dtype=torch.bfloat16) * 0.05)(B, S, D)),
            "wqkv": _w((lambda *s: torch.randn(*s, dtype=torch.bfloat16) * 0.8)(D, 3 * D)),
            "wo": _w((lambda *s: torch.randn(*s, dtype=torch.bfloat16) * 0.05)(D, D)),
        }
    _B_in = _B_setup()

    return {
        "A_x": _A_in["x"],
        "A_wqkv": _A_in["wqkv"],
        "A_wo": _A_in["wo"],
        "B_x": _B_in["x"],
        "B_wqkv": _B_in["wqkv"],
        "B_wo": _B_in["wo"],
        "gate_w": _w((lambda *s: torch.randn(*s, dtype=torch.bfloat16) * 0.05)(512) * 16.0),
    }

def reference(A_x, A_wqkv, A_wo, B_x, B_wqkv, B_wo, gate_w):
    def _A_ref(x, wqkv, wo):
        B, S, D = x.shape
        H = 32; Dh = D // H
        qkv = (lambda x, *d: x.permute(*d))((x @ wqkv).reshape(B, S, 3, H, Dh), 2, 0, 3, 1, 4)
        q, k, v = qkv[0], qkv[1], qkv[2]
        phi = lambda t: torch.where(t > 0, t + 1, torch.exp(t)) + 1e-6
        pq, pk = phi(q), phi(k)
        kv = torch.einsum("bhsd,bhse->bhde", pk, v)
        z = torch.einsum("bhsd->bhd", pk)
        num = torch.einsum("bhqd,bhde->bhqe", pq, kv)
        den = torch.einsum("bhqd,bhd->bhq", pq, z)[..., None] + 1e-6
        o = num / den
        return (lambda x, *d: x.permute(*d))(o, 0, 2, 1, 3).reshape(B, S, D) @ wo

    def _B_ref(x, wqkv, wo):
        B, S, D = x.shape
        H = 32; Dh = D // H
        qkv = (lambda x, *d: x.permute(*d))((x @ wqkv).reshape(B, S, 3, H, Dh), 2, 0, 3, 1, 4)
        q, k, v = qkv[0], qkv[1], qkv[2]
        phi = lambda t: torch.where(t > 0, t + 1, torch.exp(t)) + 1e-6
        pq, pk = phi(q), phi(k)
        kv = torch.einsum("bhsd,bhse->bhde", pk, v)
        z = torch.einsum("bhsd->bhd", pk)
        num = torch.einsum("bhqd,bhde->bhqe", pq, kv)
        den = torch.einsum("bhqd,bhd->bhq", pq, z)[..., None] + 1e-6
        o = num / den
        return (lambda x, *d: x.permute(*d))(o, 0, 2, 1, 3).reshape(B, S, D) @ wo

    x = A_x
    g = _sigmoid((x * gate_w).sum(-1, keepdims=True))
    a = _A_ref(x, A_wqkv, A_wo)
    b = _B_ref(x, B_wqkv, B_wo)
    return g * a + (1 - g) * b
```

```cpp
#include <cuda_runtime.h>
#include <cuda_bf16.h>
#include <cuda.h>
#include <stdint.h>

namespace {

#define PACE0 (B_KDONE + 3)
#define PACE1 (B_KDONE + 5)
#define PACE2 (B_KDONE + 7)
#define PACE3 (B_KDONE + 7)
#define PACEB (B_KDONE + 14)
#define GDELAY 1300
#define GTRIG 6
#define SDELAY 0
#define WOHOLD 8
#define OHOLD 2
#define HACK 0
#define EPRIO 0
#define PF2 7
#define PROMO_X CU_TENSOR_MAP_L2_PROMOTION_L2_128B
#define PROMO_W CU_TENSOR_MAP_L2_PROMOTION_L2_128B
#define NPRE 2

constexpr uint32_t OFF_X = 0;
constexpr uint32_t OFF_KVOP = 9 * 16384, OFF_GATE = OFF_KVOP + 4096;
constexpr uint32_t OFF_V = 13 * 16384;
constexpr uint32_t OFF_ONES = 14 * 16384;
constexpr uint32_t OFF_BAR = OFF_ONES + 2048;
constexpr uint32_t SMEM_BYTES = OFF_BAR + 1024;
__host__ __device__ constexpr uint32_t off_stage(int rd) { return rd ? 8 * 16384 : 10 * 16384; }
constexpr unsigned long long KV_BUF = 0xdcb8dcb9cdba9cdbull, KV_PRE = 0xba90075021000000ull;
constexpr uint32_t Q_BUF = 0xcb98a898u;

constexpr int B_XFULL = 0;
constexpr int B_KFULL = 8;
constexpr int B_QFULL = 24;
constexpr int B_ZOK = 32;
constexpr int B_KVRDY = 33;
constexpr int B_OSTORED = 35;
constexpr int B_KDONE = 40;
constexpr int B_QDONE = 56;
constexpr int B_CDONE = 64;
constexpr int B_EDONE = 72;
constexpr int B_OSTEP = 74;
constexpr int B_OSTG = 76;
constexpr int B_ALLDONE = 78;
constexpr int B_CFULL = 80;

constexpr unsigned long long CHUNK_BUF = 0xD29A1CB80D9ACBDAull;
constexpr unsigned long long pre5(int a, int b, int c, int d, int e, int f, int g) {
    return ((unsigned long long)(a - B_QDONE) << 5) | ((unsigned long long)(b - B_QDONE) << 10) | ((unsigned long long)(c - B_QDONE) << 15) |
           ((unsigned long long)(d - B_QDONE) << 20) | ((unsigned long long)(e - B_QDONE) << 25) | ((unsigned long long)(f - B_QDONE) << 30) |
           ((unsigned long long)(g - B_QDONE) << 35);
}
constexpr unsigned long long CHUNK_PRE0 = pre5(B_EDONE + 1, B_QDONE + 6, B_QDONE + 7, B_CDONE, B_OSTEP + 1, B_CDONE + 1, B_CDONE + 1);
constexpr unsigned long long CHUNK_PRE1 = pre5(B_CDONE + 2, B_CDONE + 3, B_CDONE + 3, B_CDONE + 4, B_CDONE + 5, B_CDONE + 5, B_CDONE + 6);

struct Params {
    CUtensorMap mx, mwA, mwB, moA, moB;
    const __nv_bfloat16* gate_w;
    __nv_bfloat16* out;
};

__device__ float4 g_kv[64 * 80];
__device__ uint4 g_obuf[16 * 16 * 1024];
__device__ unsigned g_zflag[8 * 32];
__device__ unsigned g_oflag[32 * 32];
__device__ uint2 g_gate[2048];
__device__ unsigned g_epoch;
#define STAMP(i) do {} while (0)
#define STAMPIF(i, cond) do {} while (0)
#define STAMP1(i) do {} while (0)
#define STAMPC(i, cond) do {} while (0)

__device__ __forceinline__ void mbar_init(uint32_t bar, uint32_t cnt) { asm volatile("mbarrier.init.shared::cta.b64 [%0], %1;" :: "r"(bar), "r"(cnt) : "memory"); }
__device__ __forceinline__ void mbar_expect_tx(uint32_t bar, uint32_t bytes) { asm volatile("mbarrier.arrive.expect_tx.shared::cta.b64 _, [%0], %1;" :: "r"(bar), "r"(bytes) : "memory"); }
__device__ __forceinline__ void mbar_arrive(uint32_t bar) { asm volatile("mbarrier.arrive.shared::cta.b64 _, [%0];" :: "r"(bar) : "memory"); }
__device__ __forceinline__ void mbar_wait_bounded(uint32_t bar) {
    asm volatile(
        "{\n .reg .pred p; .reg .u32 n;\n mov.u32 n, 0;\n"
        "W_LOOP:\n"
        " mbarrier.try_wait.parity.shared::cta.b64 p, [%0], 0;\n"
        " @p bra W_DONE;\n"
        " add.u32 n, n, 1;\n setp.lt.u32 p, n, 0x400000;\n @p bra W_LOOP;\n trap;\n"
        "W_DONE:\n}" :: "r"(bar) : "memory");
}
__device__ __forceinline__ void mbar_wait(uint32_t bar) {
    asm volatile("{\n .reg .pred p;\n W_LOOP:\n mbarrier.try_wait.parity.shared::cta.b64 p, [%0], 0;\n @!p bra W_LOOP;\n}" :: "r"(bar) : "memory");
}
__device__ __forceinline__ bool elect_one() {
    uint32_t p;
    asm volatile("{ .reg .pred P; elect.sync _|P, 0xffffffff; selp.u32 %0, 1, 0, P; }" : "=r"(p));
    return p;
}
__device__ __forceinline__ void tma_2d(uint32_t dst, const CUtensorMap* m, int c0, int c1, uint32_t bar) {
    asm volatile("cp.async.bulk.tensor.2d.shared::cluster.global.mbarrier::complete_tx::bytes [%0], [%1, {%3, %4}], [%2];"
        :: "r"(dst), "l"(m), "r"(bar), "r"(c0), "r"(c1) : "memory");
}
__device__ __forceinline__ void tma_prefetch_2d(const CUtensorMap* m, int c0, int c1) {
    asm volatile("cp.async.bulk.prefetch.tensor.2d.L2.global [%0, {%1, %2}];" :: "l"(m), "r"(c0), "r"(c1) : "memory");
}
__device__ __forceinline__ void bulk_load(uint32_t dst, const void* src, uint32_t bytes, uint32_t bar) {
    asm volatile("cp.async.bulk.shared::cluster.global.mbarrier::complete_tx::bytes [%0], [%1], %2, [%3];"
        :: "r"(dst), "l"(src), "r"(bytes), "r"(bar) : "memory");
}
__device__ __forceinline__ void bulk_store(void* dst, uint32_t src, uint32_t bytes) {
    asm volatile("cp.async.bulk.global.shared::cta.bulk_group [%0], [%1], %2;" :: "l"(dst), "r"(src), "r"(bytes) : "memory");
}
__device__ __forceinline__ void bulk_commit() { asm volatile("cp.async.bulk.commit_group;" ::: "memory"); }
__device__ __forceinline__ void bulk_wait_all() { asm volatile("cp.async.bulk.wait_group 0;" ::: "memory"); }
__device__ __forceinline__ void fence_async_smem() { asm volatile("fence.proxy.async.shared::cta;" ::: "memory"); }
__device__ __forceinline__ void fence_async_global() { asm volatile("fence.proxy.async.global;" ::: "memory"); }
__device__ __forceinline__ uint32_t clk32() { uint32_t c; asm volatile("mov.u32 %0, %%clock;" : "=r"(c) :: "memory"); return c; }
__device__ __forceinline__ void spin(uint32_t clks) { const uint32_t t0 = clk32(); while (clk32() - t0 < clks) {} }
__device__ __forceinline__ unsigned ld_relaxed(const unsigned* p) { unsigned v; asm volatile("ld.relaxed.gpu.global.u32 %0, [%1];" : "=r"(v) : "l"(p) : "memory"); return v; }
__device__ __forceinline__ void st_relaxed(unsigned* p, unsigned v) { asm volatile("st.relaxed.gpu.global.u32 [%0], %1;" :: "l"(p), "r"(v) : "memory"); }
__device__ __forceinline__ void red_add_v4(float4* p, float a, float b, float c, float d) {
    asm volatile("red.relaxed.gpu.global.add.v4.f32 [%0], {%1, %2, %3, %4};" :: "l"(p), "f"(a), "f"(b), "f"(c), "f"(d) : "memory");
}
__device__ __forceinline__ float4 ld_relaxed4(const float4* p) {
    float4 v;
    asm volatile("ld.relaxed.gpu.global.v4.f32 {%0, %1, %2, %3}, [%4];" : "=f"(v.x), "=f"(v.y), "=f"(v.z), "=f"(v.w) : "l"(p) : "memory");
    return v;
}
__device__ __forceinline__ void poll_eq(const unsigned* p, unsigned target) {
    unsigned v0 = ld_relaxed(p); spin(200);
    unsigned v1 = ld_relaxed(p); spin(200);
    unsigned v2 = ld_relaxed(p);
    for (int n = 0;; n++) {
        if (__all_sync(~0u, v0 == target)) break;
        v0 = ld_relaxed(p);
        if (__all_sync(~0u, v1 == target)) break;
        v1 = ld_relaxed(p);
        if (__all_sync(~0u, v2 == target)) break;
        v2 = ld_relaxed(p);
        if (n > (1 << 20)) __trap();
    }
}
__device__ __forceinline__ void nbar_sync(int id, int n) { asm volatile("bar.sync %0, %1;" :: "r"(id), "r"(n) : "memory"); }
__device__ __forceinline__ void nbar_arrive(int id, int n) { asm volatile("bar.arrive %0, %1;" :: "r"(id), "r"(n) : "memory"); }
__device__ __forceinline__ uint32_t pack_bf16(float lo, float hi) { uint32_t r; asm("cvt.rn.bf16x2.f32 %0, %1, %2;" : "=r"(r) : "f"(hi), "f"(lo)); return r; }
__device__ __forceinline__ float rcp_fast(float x) { float r; asm("rcp.approx.ftz.f32 %0, %1;" : "=f"(r) : "f"(x)); return r; }
__device__ __forceinline__ float ex2_fast(float x) { float r; asm("ex2.approx.ftz.f32 %0, %1;" : "=f"(r) : "f"(x)); return r; }
__device__ __forceinline__ void stmatrix_x4(uint32_t addr, uint32_t a, uint32_t b, uint32_t c, uint32_t d) {
    asm volatile("stmatrix.sync.aligned.m8n8.x4.shared.b16 [%0], {%1, %2, %3, %4};" :: "r"(addr), "r"(a), "r"(b), "r"(c), "r"(d) : "memory");
}
__device__ __forceinline__ void stmatrix_x4_t(uint32_t addr, uint32_t a, uint32_t b, uint32_t c, uint32_t d) {
    asm volatile("stmatrix.sync.aligned.m8n8.x4.trans.shared.b16 [%0], {%1, %2, %3, %4};" :: "r"(addr), "r"(a), "r"(b), "r"(c), "r"(d) : "memory");
}
__device__ __forceinline__ void sts32(uint32_t addr, uint32_t v) { asm volatile("st.shared.u32 [%0], %1;" :: "r"(addr), "r"(v) : "memory"); }
__device__ __forceinline__ void sts128(uint32_t addr, uint4 v) { asm volatile("st.shared.v4.u32 [%0], {%1, %2, %3, %4};" :: "r"(addr), "r"(v.x), "r"(v.y), "r"(v.z), "r"(v.w) : "memory"); }
__device__ __forceinline__ uint4 lds128(uint32_t addr) { uint4 v; asm volatile("ld.shared.v4.u32 {%0, %1, %2, %3}, [%4];" : "=r"(v.x), "=r"(v.y), "=r"(v.z), "=r"(v.w) : "r"(addr) : "memory"); return v; }
__device__ __forceinline__ uint32_t phi2(float t0, float t1) {
    float s0, s1;
    uint32_t m, r;
    asm("add.sat.f32 %0, %1, %2;" : "=f"(s0) : "f"(ex2_fast(t0 * 1.4426950408889634f)), "f"(1e-6f));
    asm("add.sat.f32 %0, %1, %2;" : "=f"(s1) : "f"(ex2_fast(t1 * 1.4426950408889634f)), "f"(1e-6f));
    asm("cvt.rn.relu.bf16x2.f32 %0, %1, %2;" : "=r"(m) : "f"(t1), "f"(t0));
    asm("add.rn.bf16x2 %0, %1, %2;" : "=r"(r) : "r"(pack_bf16(s0, s1)), "r"(m));
    return r;
}

__device__ __forceinline__ void wg_fence() { asm volatile("wgmma.fence.sync.aligned;" ::: "memory"); }
__device__ __forceinline__ void wg_commit() { asm volatile("wgmma.commit_group.sync.aligned;" ::: "memory"); }
template <int N> __device__ __forceinline__ void wg_wait() { asm volatile("wgmma.wait_group.sync.aligned %0;" :: "n"(N) : "memory"); }
__device__ __forceinline__ uint32_t desc_lo(uint32_t addr) { return (addr >> 4) | 0x10000u; }
#define ACC8(d, o) "+f"(d[o]), "+f"(d[o + 1]), "+f"(d[o + 2]), "+f"(d[o + 3]), "+f"(d[o + 4]), "+f"(d[o + 5]), "+f"(d[o + 6]), "+f"(d[o + 7])
template <int ACC>
__device__ __forceinline__ void wgmma_n128(float (&d)[64], uint32_t da, uint32_t db) {
    asm volatile("{ .reg .b64 a, b; mov.b64 a, {%64, 0x40000040}; mov.b64 b, {%65, 0x40000040};\n"
        "wgmma.mma_async.sync.aligned.m64n128k16.f32.bf16.bf16 "
        "{%0, %1, %2, %3, %4, %5, %6, %7, %8, %9, %10, %11, %12, %13, %14, %15, %16, %17, %18, %19, %20, %21, %22, %23, %24, %25, %26, %27, %28, %29, %30, %31, "
        "%32, %33, %34, %35, %36, %37, %38, %39, %40, %41, %42, %43, %44, %45, %46, %47, %48, %49, %50, %51, %52, %53, %54, %55, %56, %57, %58, %59, %60, %61, %62, %63}, "
        "a, b, %66, 1, 1, 1, 0; }"
        : ACC8(d, 0), ACC8(d, 8), ACC8(d, 16), ACC8(d, 24), ACC8(d, 32), ACC8(d, 40), ACC8(d, 48), ACC8(d, 56)
        : "r"(da), "r"(db), "n"(ACC));
}
template <int ACC>
__device__ __forceinline__ void wgmma_n72_rs(float (&d)[36], uint32_t a0, uint32_t a1, uint32_t a2, uint32_t a3, uint32_t db) {
    asm volatile("{ .reg .b64 b; mov.b64 b, {%40, 0x40000080};\n"
        "wgmma.mma_async.sync.aligned.m64n72k16.f32.bf16.bf16 "
        "{%0, %1, %2, %3, %4, %5, %6, %7, %8, %9, %10, %11, %12, %13, %14, %15, %16, %17, %18, %19, %20, %21, %22, %23, %24, %25, %26, %27, %28, %29, %30, %31, "
        "%32, %33, %34, %35}, {%36, %37, %38, %39}, b, %41, 1, 1, 0; }"
        : ACC8(d, 0), ACC8(d, 8), ACC8(d, 16), ACC8(d, 24), "+f"(d[32]), "+f"(d[33]), "+f"(d[34]), "+f"(d[35])
        : "r"(a0), "r"(a1), "r"(a2), "r"(a3), "r"(db), "n"(ACC));
}
__device__ __forceinline__ void wgmma_n24(float (&d)[12], uint32_t da, uint32_t db) {
    asm volatile("{ .reg .b64 a, b; mov.b64 a, {%12, 0x40000040}; mov.b64 b, {%13, 0x00000010};\n"
        "wgmma.mma_async.sync.aligned.m64n24k16.f32.bf16.bf16 {%0, %1, %2, %3, %4, %5, %6, %7, %8, %9, %10, %11}, a, b, 0, 1, 1, 1, 1; }"
        : ACC8(d, 0), "+f"(d[8]), "+f"(d[9]), "+f"(d[10]), "+f"(d[11]) : "r"(da), "r"(db));
}

template <int FIRST>
__device__ __forceinline__ void gemm_pair(float (&qa)[64], uint32_t da, uint32_t db) {
    wg_fence();
    wgmma_n128<!FIRST>(qa, da, db);
#pragma unroll
    for (int kk = 1; kk < 8; kk++) wgmma_n128<1>(qa, da + kk * 128, db + (kk >> 2) * 1024 + (kk & 3) * 2);
    wg_commit();
}

__global__ void __launch_bounds__(384, 1) fused_kernel(const __grid_constant__ Params p) {
    extern __shared__ __align__(1024) uint8_t smem_raw[];
    const uint32_t sb = (uint32_t)__cvta_generic_to_shared(smem_raw);
    const uint32_t bars = sb + OFF_BAR;
    const int warp = __shfl_sync(~0u, threadIdx.x >> 5, 0), lane = threadIdx.x & 31;
    const int grp = blockIdx.x >> 3, gi = blockIdx.x & 7;
    const int branch = grp >> 3, r = (grp & 7) * 2 + (gi & 1), cl = gi >> 1, c = branch * 4 + cl;
    STAMPIF(0, warp == 0);
    const CUtensorMap* mw = branch ? &p.mwB : &p.mwA;

    if (warp == 8) {
        if (elect_one()) {
#pragma unroll
            for (int i = 0; i < 8; i++) mbar_init(bars + 8 * (B_XFULL + i), 1);
#pragma unroll 1
            for (int j = 0; j < 8; j++) {
                mbar_expect_tx(bars + 8 * (B_XFULL + j), 16384);
                tma_2d(sb + OFF_X + j * 16384, &p.mx, j * 64, r * 128, bars + 8 * (B_XFULL + j));
            }
        }
    } else if (warp == 9) {
        if (elect_one()) {
#pragma unroll
            for (int i = 0; i < 8; i++) mbar_init(bars + 8 * (B_KFULL + i), 1);
            uint32_t tb = (uint32_t)KV_BUF;
#pragma unroll 1
            for (int j = 0; j < 5; j++) {
                const uint32_t bar = bars + 8 * (B_KFULL + j), dst = sb + (tb & 15) * 16384;
                mbar_expect_tx(bar, HACK & 2 ? 8192 : 16384);
                tma_2d(dst, mw, 512 + (j & 4) * 128 + cl * 128, (j & 3) * 128, bar);
                if (!(HACK & 2)) tma_2d(dst + 8192, mw, 512 + (j & 4) * 128 + cl * 128, (j & 3) * 128 + 64, bar);
                tb >>= 4;
            }
        }
    } else {
        if (warp < 4) sts128(sb + OFF_ONES + threadIdx.x * 16, make_uint4(0x3f803f80u, 0x3f803f80u, 0x3f803f80u, 0x3f803f80u));
        if (elect_one()) {
            const int bg = warp < 8 ? warp + 2 : warp;
            const uint32_t bar = bars + 64 * bg, cnt = bg < 5 || bg >= 10 ? 1 : 4;
            mbar_init(bar, bg == 4 ? 6 : bg >= 10 ? 5 : cnt);
#pragma unroll
            for (int i = 1; i < 8; i++) mbar_init(bar + 8 * i, cnt);
        }
        fence_async_smem();
    }
    __syncwarp();
    __syncthreads();

    if (warp < 8) {
        asm volatile("setmaxnreg.inc.sync.aligned.u32 208;");
        const int wq = warp & 3;
        const int g = lane >> 2, q = lane & 3;
        const uint32_t dx = desc_lo(sb + OFF_X);
        const uint32_t sw = ((lane >> 4) ^ (lane & 7)) << 4;
        const bool lead = elect_one();
        if (warp < 4) {
            uint32_t ktb = (uint32_t)KV_BUF;
#pragma unroll 1
            for (int rd = 0; rd < 2; rd++) {
                float acc[64], va[64];
                const uint32_t kb = bars + 64 * rd;
                mbar_wait(bars + 8 * B_XFULL);
                mbar_wait(bars + 8 * (B_XFULL + 1));
                mbar_wait(kb + 8 * B_KFULL);
                STAMP(1 + rd * 5);
                STAMP(30 + 8 * rd);
                gemm_pair<1>(acc, dx + (ktb & 15) * 1024, dx);
#pragma unroll 1
                for (int pr = 1; pr < 4; pr++) {
                    mbar_wait(bars + 8 * (B_XFULL + 2 * pr));
                    mbar_wait(bars + 8 * (B_XFULL + 2 * pr + 1));
                    mbar_wait(kb + 8 * (B_KFULL + pr));
                    STAMP(30 + 8 * rd + pr);
                    gemm_pair<0>(acc, dx + ((ktb >> (4 * pr)) & 15) * 1024, dx + pr * 2048);
                    wg_wait<1>();
                    if (lead) mbar_arrive(kb + 8 * (B_KDONE + pr - 1));
                }
                uint32_t pk[32];
                mbar_wait(kb + 8 * (B_KFULL + 4));
                STAMP(34 + 8 * rd);
                gemm_pair<1>(va, dx + ((ktb >> 16) & 15) * 1024, dx);
                wg_wait<1>();
                if (lead) mbar_arrive(kb + 8 * (B_KDONE + 3));
#define PHI_PART(I) _Pragma("unroll") for (int i = 8 * I; i < 8 * I + 8; i++) pk[i] = phi2(acc[2 * i], acc[2 * i + 1]);
#define V_STEP(PR)                                                                               \
                mbar_wait(kb + 8 * (B_KFULL + 4 + PR));                                          \
                STAMP(34 + 8 * rd + PR);                                                         \
                gemm_pair<0>(va, dx + ((ktb >> (16 + 4 * PR)) & 15) * 1024, dx + PR * 2048);     \
                PHI_PART(PR)                                                                     \
                wg_wait<1>();                                                                    \
                if (lead) mbar_arrive(kb + 8 * (B_KDONE + 3 + PR));
                PHI_PART(0) V_STEP(1) V_STEP(2) V_STEP(3)
                ktb = (uint32_t)(KV_BUF >> 32);
                wg_wait<0>();
                if (lead) mbar_arrive(kb + 8 * (B_KDONE + 7));
                STAMP(2 + rd * 5);
                const uint32_t vrow = sb + OFF_V + (wq * 2 + ((lane >> 3) & 1)) * 2048 + (lane & 7) * 128;
#pragma unroll
                for (int t = 0; t < 8; t++)
                    stmatrix_x4(vrow + (t >> 2) * 1024 + (sw ^ ((t & 3) << 5)),
                                pack_bf16(va[8 * t], va[8 * t + 1]), pack_bf16(va[8 * t + 2], va[8 * t + 3]),
                                pack_bf16(va[8 * t + 4], va[8 * t + 5]), pack_bf16(va[8 * t + 6], va[8 * t + 7]));
                fence_async_smem();
                nbar_sync(1, 128);
                STAMP(3 + rd * 5);
                float e[36];
                wg_fence();
                const uint32_t dv = desc_lo(sb + OFF_V);
                wgmma_n72_rs<0>(e, pk[0], pk[1], pk[2], pk[3], dv);
#pragma unroll
                for (int t = 1; t < 8; t++) wgmma_n72_rs<1>(e, pk[4 * t], pk[4 * t + 1], pk[4 * t + 2], pk[4 * t + 3], dv + (t >> 2) * 64 + (t & 3) * 2);
                wg_commit();
                if (rd) nbar_arrive(4, 256);
                wg_wait<0>();
                STAMP(4 + rd * 5);
                float kv[8];
#pragma unroll
                for (int i = 0; i < 8; i++) kv[i] = wq & 2 ? (wq & 1 ? e[24 + i] : e[16 + i]) : (wq & 1 ? e[8 + i] : e[i]);
                float4* kvp = g_kv + (c * 8 + rd * 4 + wq) * 80;
                mbar_wait(bars + 8 * B_ZOK);
                red_add_v4(kvp + lane, kv[0], kv[1], kv[2], q & 1 ? 1.f : kv[3]);
                red_add_v4(kvp + 32 + lane, kv[4], kv[5], kv[6], q & 1 ? 1.f : kv[7]);
                if (q & 1) red_add_v4(kvp + 64 + (lane >> 1), kv[3], kv[7], q & 2 ? e[34] : e[32], 1.f);
                if (lead) mbar_arrive(bars + 8 * (B_EDONE + rd));
                STAMP(5 + rd * 5);
            }
            float acc[64];
#pragma unroll
            for (int i = 0; i < 64; i++) acc[i] = 0.f;
            unsigned long long tbl = CHUNK_BUF;
            nbar_sync(2, 256);
#pragma unroll 1
            for (int n = 0; n < 16; n++) {
                if (n == NPRE) {
                    wg_wait<0>();
                    if (NPRE > 0 && lead) mbar_arrive(bars + 8 * (B_CDONE + NPRE - 1));
                    mbar_wait(bars + 8 * B_OSTORED);
                }
                mbar_wait(bars + 8 * (B_CFULL + n));
                STAMPIF(11, n == 0); STAMPIF(12, n == 1); STAMPIF(13, n == NPRE); STAMPIF(14, n == 8); STAMPIF(15, n == 9);
                const uint32_t db = dx + ((uint32_t)tbl & 15) * 1024, dw = dx + n * 512;
                tbl >>= 4;
                wg_fence();
#pragma unroll
                for (int kk = 0; kk < 4; kk++) wgmma_n128<1>(acc, dw + kk * 128, db + kk * 2);
                wg_commit();
                wg_wait<1>();
                if (n > 0 && n < 8 && n != NPRE && lead) mbar_arrive(bars + 8 * (B_CDONE + n - 1));
            }
            wg_wait<0>();
            STAMP(16);
            const uint32_t stg = sb + OFF_X + 49152 + wq * 4096;
#pragma unroll
            for (int j = 0; j < 8; j++) {
                const int row = 16 * j + (lane & 7) + ((lane >> 4) << 3);
                stmatrix_x4_t(stg + row * 32 + ((((lane >> 3) ^ (lane >> 2)) & 1) << 4),
                              pack_bf16(acc[8 * j], acc[8 * j + 1]), pack_bf16(acc[8 * j + 2], acc[8 * j + 3]),
                              pack_bf16(acc[8 * j + 4], acc[8 * j + 5]), pack_bf16(acc[8 * j + 6], acc[8 * j + 7]));
            }
            __syncwarp();
            uint4* op = reinterpret_cast<uint4*>(p.out + (r * 128 + (lane >> 1)) * 512 + c * 64 + wq * 16) + (lane & 1);
#pragma unroll
            for (int j = 0; j < 8; j++) op[j * 1024] = lds128(stg + j * 512 + (lane >> 1) * 32 + (((lane ^ (lane >> 3)) & 1) << 4));
            STAMP(17);
            if (lead) mbar_arrive(bars + 8 * B_ALLDONE);
        } else {
            {
                const unsigned tgt = ld_relaxed(&g_epoch) + 1;
                const int f = g & 1;
                const uint4 w0 = __ldg(reinterpret_cast<const uint4*>(p.gate_w) + 2 * lane + f), w1 = __ldg(reinterpret_cast<const uint4*>(p.gate_w) + 2 * lane + 1 - f);
                const uint32_t wr[8] = {w0.x, w0.y, w0.z, w0.w, w1.x, w1.y, w1.z, w1.w};
                const uint32_t xa = sb + OFF_X + g * 16384 + c * 2048 + wq * 512, ch = (2 * q + f) ^ ((wq & 1) << 2);
#pragma unroll 1
                for (int j = 0; j < 8; j++) mbar_wait(bars + 8 * (B_XFULL + j));
                float a[4] = {0.f, 0.f, 0.f, 0.f};
#pragma unroll
                for (int u = 0; u < 4; u++) {
                    const uint32_t ad = xa + u * 128 + ((ch ^ u) << 4);
                    const uint4 x0 = lds128(ad), x1 = lds128(ad ^ 16);
                    const uint32_t x[8] = {x0.x, x0.y, x0.z, x0.w, x1.x, x1.y, x1.z, x1.w};
#pragma unroll
                    for (int k = 0; k < 8; k++) {
                        a[u] = fmaf(__uint_as_float(x[k] << 16), __uint_as_float(wr[k] << 16), a[u]);
                        a[u] = fmaf(__uint_as_float(x[k] & 0xffff0000u), __uint_as_float(wr[k] & 0xffff0000u), a[u]);
                    }
                }
                const float t0 = (lane & 16 ? a[2] : a[0]) + __shfl_xor_sync(~0u, lane & 16 ? a[0] : a[2], 16);
                const float t1 = (lane & 16 ? a[3] : a[1]) + __shfl_xor_sync(~0u, lane & 16 ? a[1] : a[3], 16);
                float t = (lane & 8 ? t1 : t0) + __shfl_xor_sync(~0u, lane & 8 ? t0 : t1, 8);
#pragma unroll
                for (int s = 4; s >= 1; s >>= 1) t += __shfl_xor_sync(~0u, t, s);
                if ((lane & 7) == 0)
                    asm volatile("st.relaxed.gpu.global.v2.b32 [%0], {%1, %2};" :: "l"(g_gate + r * 128 + c * 16 + wq * 4 + (lane >> 3)), "r"(__float_as_uint(t)), "r"(tgt) : "memory");
                if (lead) mbar_arrive(bars + 8 * B_ZOK);
            }
            uint32_t qtb = Q_BUF;
#pragma unroll 1
            for (int rd = 0; rd < 2; rd++) {
                float acc[64];
                const uint32_t qb = bars + 32 * rd;
                mbar_wait(bars + 8 * (rd ? PACEB : PACE0));
                mbar_wait(qb + 8 * B_QFULL);
                if (rd && EPRIO == 0) nbar_sync(4, 256);
                STAMP(18 + rd * 6);
                STAMP(46 + 4 * rd);
                gemm_pair<1>(acc, dx + (qtb & 15) * 1024, dx);
#pragma unroll 1
                for (int pr = 1; pr < 4; pr++) {
                    const bool paced = rd == 0 && pr < 3;
                    if (paced) { wg_wait<0>(); if (lead) mbar_arrive(qb + 8 * (B_QDONE + pr - 1)); }
                    mbar_wait(bars + 8 * (pr == 1 ? PACE1 : pr == 2 ? PACE2 : PACE3));
                    mbar_wait(qb + 8 * (B_QFULL + pr));
                    if (rd && pr == EPRIO) nbar_sync(4, 256);
                    qtb >>= 4;
                    STAMP(46 + 4 * rd + pr);
                    gemm_pair<0>(acc, dx + (qtb & 15) * 1024, dx + pr * 2048);
                    if (rd && pr == 3) nbar_arrive(2, 256);
                    wg_wait<1>();
                    if (!paced && lead) mbar_arrive(qb + 8 * (B_QDONE + pr - 1));
                }
                qtb >>= 4;
                wg_wait<0>();
                if (lead) mbar_arrive(qb + 8 * (B_QDONE + 3));
                STAMP(19 + rd * 6);
                const uint32_t stg = sb + off_stage(rd);
                const uint32_t srow = stg + (wq * 16 + (lane & 15)) * 128;
#pragma unroll
                for (int t = 0; t < 8; t++)
                    stmatrix_x4(srow + (t >> 2) * 8192 + (sw ^ ((t & 3) << 5)),
                                phi2(acc[8 * t], acc[8 * t + 1]), phi2(acc[8 * t + 2], acc[8 * t + 3]),
                                phi2(acc[8 * t + 4], acc[8 * t + 5]), phi2(acc[8 * t + 6], acc[8 * t + 7]));
                fence_async_smem();
                nbar_sync(3, 128);
                STAMP(20 + rd * 6);
                mbar_wait(bars + 8 * (B_KVRDY + rd));
                STAMP(21 + rd * 6);
                float gt[4];
#pragma unroll
                for (int i = 0; i < 4; i++)
                    asm volatile("ld.shared.f32 %0, [%1];" : "=f"(gt[i]) : "r"(sb + OFF_GATE + 4 * ((i >> 1) * 64 + wq * 16 + (i & 1) * 8 + g)));
                float o[8][12];
                const uint32_t dp = desc_lo(stg), dk = ((sb + OFF_KVOP) >> 4) | 0x80000u;
                wg_fence();
#pragma unroll
                for (int i = 0; i < 8; i++) wgmma_n24(o[i], dp + (i >> 2) * 512 + (i & 3) * 128, dk + (i & 3) * 48);
                wg_commit();
                wg_wait<0>();
                if (lead) mbar_arrive(bars + 8 * (B_OSTEP + rd));
                nbar_sync(3, 128);
                STAMP(22 + rd * 6);
#pragma unroll
                for (int i = 0; i < 8; i++) {
                    const float slo = gt[2 * (i >> 2)] * rcp_fast(o[i][8] + 1e-6f), shi = gt[2 * (i >> 2) + 1] * rcp_fast(o[i][10] + 1e-6f);
                    stmatrix_x4(srow + (i >> 2) * 8192 + (sw ^ ((i & 3) << 5)),
                                pack_bf16(o[i][0] * slo, o[i][1] * slo), pack_bf16(o[i][2] * shi, o[i][3] * shi),
                                pack_bf16(o[i][4] * slo, o[i][5] * slo), pack_bf16(o[i][6] * shi, o[i][7] * shi));
                }
                fence_async_smem();
                __syncwarp();
                if (lead) { mbar_arrive(bars + 8 * (B_OSTG + rd)); mbar_arrive(bars + 8 * (B_CFULL + 8 * rd)); }
                STAMP(23 + rd * 6);
            }
        }
    } else {
        asm volatile("setmaxnreg.dec.sync.aligned.u32 88;");
        if (warp == 8) {
            if (elect_one()) {
#pragma unroll 1
                for (int i = 0; i < 8; i++) {
                    const int pre = i == 1 ? B_KDONE + 3 : i == 3 ? B_KDONE + 4 : i == 2 ? B_QDONE : i == 4 ? B_KDONE + 12 : i == 5 ? B_OSTEP : B_KDONE + 7 + i;
                    if (i) mbar_wait(bars + 8 * pre);
                    const uint32_t bar = bars + 8 * (B_QFULL + i), dst = sb + ((Q_BUF >> (4 * i)) & 15) * 16384;
                    mbar_expect_tx(bar, HACK & 2 ? 8192 : 16384);
                    tma_2d(dst, mw, cl * 128 + (i >> 2) * 64, (i & 3) * 128, bar);
                    if (!(HACK & 2)) tma_2d(dst + 8192, mw, cl * 128 + (i >> 2) * 64, (i & 3) * 128 + 64, bar);
                }
                mbar_wait(bars + 8 * (B_KDONE + 15));
#pragma unroll 1
                for (int n = 0; n < 16; n++) {
                    if ((n & 3) == 0) mbar_wait(bars + 8 * (B_QDONE + 4 + (n >> 2)));
                    if (n == WOHOLD) mbar_wait(bars + 8 * (B_KVRDY + 1));
                    const int m = n & 7, cc = m == 0 ? c : (m - 1 < c ? m - 1 : m);
                    STAMPC(60, n == 15);
                    if (!(HACK & 4)) tma_2d(sb + OFF_X + n * 8192, cc >= 4 ? &p.moB : &p.moA, c * 64, (cc & 3) * 128 + (n >> 3) * 64, bars + 8 * (B_CFULL + n));
                }
            }
        } else {
            const unsigned tgt = ld_relaxed(&g_epoch) + 1;
            if (tgt == 0) __trap();
            if (warp == 9) {
                if (elect_one()) {
#pragma unroll 1
                    for (int j = 5; j < 16; j++) {
                        mbar_wait(bars + 8 * (j == 8 ? B_QDONE + 1 : j == 12 ? B_QDONE + 2 : j == 11 ? B_EDONE : B_KDONE + ((uint32_t)(KV_PRE >> (4 * j)) & 15)));
                        const uint32_t bar = bars + 8 * (B_KFULL + j), dst = sb + ((uint32_t)(KV_BUF >> (4 * j)) & 15) * 16384;
                        mbar_expect_tx(bar, HACK & 2 ? 8192 : 16384);
                        tma_2d(dst, mw, 512 + (j & 4) * 128 + cl * 128 + (j >> 3) * 64, (j & 3) * 128, bar);
                        if (!(HACK & 2)) tma_2d(dst + 8192, mw, 512 + (j & 4) * 128 + cl * 128 + (j >> 3) * 64, (j & 3) * 128 + 64, bar);
                    }
#pragma unroll 1
                    for (int n = 0; n < 16; n++) mbar_expect_tx(bars + 8 * (B_CFULL + n), n & 7 ? (HACK & 1 ? 8192 : 16384) + (HACK & 4 ? 0 : 8192) : (HACK & 4 ? 0 : 8192));
                }
                __syncwarp();
                unsigned long long tb = CHUNK_BUF, tp = CHUNK_PRE0;
#pragma unroll 1
                for (int hf = 0; hf < 2; hf++) {
                    poll_eq(g_oflag + (r * 2 + hf) * 32 + (lane & 7), tgt);
                    STAMP(56 + hf);
                    if (elect_one()) {
                        fence_async_global();
#pragma unroll 1
                        for (int m = 1; m < 8; m++) {
                            if (m == OHOLD) mbar_wait(bars + 8 * (B_KVRDY + 1));
                            mbar_wait(bars + 8 * (B_QDONE + ((uint32_t)(tp >> (5 * m)) & 31)));
                            bulk_load(sb + ((uint32_t)(tb >> (4 * m)) & 15) * 16384, g_obuf + ((r * 2 + hf) * 8 + (m - 1 < c ? m - 1 : m)) * 1024, HACK & 1 ? 8192 : 16384,
                                      bars + 8 * (B_CFULL + hf * 8 + m));
                        }
                    }
                    tb >>= 32; tp = CHUNK_PRE1;
                    __syncwarp();
                }
                if (blockIdx.x == 0 && lane == 0) st_relaxed(&g_epoch, tgt);
            } else if (warp == 10) {
                const bool lead = elect_one();
                if (r == 0) {
                    float4* kz = g_kv + c * 640 + lane;
                    float chk = 0.f;
#pragma unroll 1
                    for (int i = 0; i < 20; i++) kz[i * 32] = make_float4(0.f, 0.f, 0.f, 0.f);
#pragma unroll
                    for (int i = 0; i < 20; i++) chk += __uint_as_float(ld_relaxed(reinterpret_cast<const unsigned*>(kz + i * 32)));
                    if (!__all_sync(~0u, chk == 0.f)) __trap();
                    if (lead) st_relaxed(g_zflag + c * 32, tgt);
                }
                poll_eq(g_zflag + c * 32, tgt);
                if (lead) mbar_arrive(bars + 8 * B_ZOK);
#pragma unroll 1
                for (int rd = 0; rd < 2; rd++) {
                    mbar_wait(bars + 8 * (B_EDONE + rd));
                    if (rd) mbar_wait(bars + 8 * (B_QDONE + GTRIG)); else spin(GDELAY);
                    const float4* kvp = g_kv + (c * 8 + rd * 4) * 80;
                    const bool odd = lane & 1;
                    const uint4* gp = reinterpret_cast<const uint4*>(g_gate + r * 128) + lane * 2;
                    float4 v[12];
                    uint4 ga, gb;
                    int n = 0;
                    while (true) {
                        bool ok = true;
                        asm volatile("ld.relaxed.gpu.global.v2.b64 {%0, %1}, [%2];" : "=l"(*(unsigned long long*)&ga.x), "=l"(*(unsigned long long*)&ga.z) : "l"(gp) : "memory");
                        asm volatile("ld.relaxed.gpu.global.v2.b64 {%0, %1}, [%2];" : "=l"(*(unsigned long long*)&gb.x), "=l"(*(unsigned long long*)&gb.z) : "l"(gp + 1) : "memory");
#pragma unroll
                        for (int h = 0; h < 4; h++) {
                            v[3 * h] = ld_relaxed4(kvp + h * 80 + lane);
                            v[3 * h + 1] = ld_relaxed4(kvp + h * 80 + 32 + lane);
                            v[3 * h + 2] = ld_relaxed4(kvp + h * 80 + 64 + (lane >> 1));
                        }
#pragma unroll
                        for (int i = 0; i < 12; i++) ok = ok && v[i].w == 16.f;
                        if (__all_sync(~0u, (ok || !odd) && ga.y == tgt && ga.w == tgt && gb.y == tgt && gb.w == tgt)) break;
                        if (++n > (1 << 20)) __trap();
                    }
                    STAMP(54 + rd);
                    mbar_wait(bars + 8 * (rd ? B_QDONE + 5 : B_KDONE + 8));
                    const float sg = branch ? 1.4426950408889634f : -1.4426950408889634f;
                    ga.x = __float_as_uint(rcp_fast(1.f + ex2_fast(__uint_as_float(ga.x) * sg)));
                    ga.y = __float_as_uint(rcp_fast(1.f + ex2_fast(__uint_as_float(ga.z) * sg)));
                    ga.z = __float_as_uint(rcp_fast(1.f + ex2_fast(__uint_as_float(gb.x) * sg)));
                    ga.w = __float_as_uint(rcp_fast(1.f + ex2_fast(__uint_as_float(gb.z) * sg)));
                    sts128(sb + OFF_GATE + lane * 16, ga);
                    const uint32_t dst = sb + OFF_KVOP + lane * 4;
#pragma unroll
                    for (int h = 0; h < 4; h++) {
                        const float4 a = v[3 * h], b = v[3 * h + 1], d = v[3 * h + 2];
                        const float z0 = __shfl_sync(~0u, d.z, lane & 28), z1 = __shfl_sync(~0u, d.z, (lane & 28) + 2);
                        sts32(dst + h * 768, pack_bf16(a.x, a.y)); sts32(dst + h * 768 + 128, pack_bf16(a.z, odd ? d.x : a.w));
                        sts32(dst + h * 768 + 256, pack_bf16(b.x, b.y)); sts32(dst + h * 768 + 384, pack_bf16(b.z, odd ? d.y : b.w));
                        sts32(dst + h * 768 + 512, pack_bf16(z0, z0)); sts32(dst + h * 768 + 640, pack_bf16(z1, z1));
                    }
                    fence_async_smem();
                    __syncwarp();
                    if (lead) mbar_arrive(bars + 8 * (B_KVRDY + rd));
                }
            } else {
                if (elect_one()) {
                    mbar_arrive(bars + 8 * B_ZOK);
#pragma unroll 1
                    for (int rd = 0; rd < 2; rd++) {
                        mbar_wait(bars + 8 * (B_OSTG + rd));
                        bulk_store(g_obuf + ((r * 2 + rd) * 8 + c) * 1024, sb + off_stage(rd), 16384);
                        bulk_commit();
                        bulk_wait_all();
                        st_relaxed(g_oflag + (r * 2 + rd) * 32 + c, tgt);
                        STAMP1(58 + rd);
                    }
                    mbar_arrive(bars + 8 * B_OSTORED);
                    mbar_wait_bounded(bars + 8 * B_ALLDONE);
                }
            }
        }
    }
}

typedef CUresult (*EncodeFn)(CUtensorMap*, CUtensorMapDataType, cuuint32_t, void*, const cuuint64_t*, const cuuint64_t*,
                             const cuuint32_t*, const cuuint32_t*, CUtensorMapInterleave, CUtensorMapSwizzle,
                             CUtensorMapL2promotion, CUtensorMapFloatOOBfill);

void make_map(EncodeFn enc, CUtensorMap* m, const void* ptr, uint64_t rows, uint64_t cols, uint32_t box_rows, CUtensorMapL2promotion promo) {
    cuuint64_t gd[2] = {cols, rows}, gs[1] = {cols * 2};
    cuuint32_t bd[2] = {64, box_rows}, es[2] = {1, 1};
    enc(m, CU_TENSOR_MAP_DATA_TYPE_BFLOAT16, 2, const_cast<void*>(ptr), gd, gs, bd, es, CU_TENSOR_MAP_INTERLEAVE_NONE,
        CU_TENSOR_MAP_SWIZZLE_128B, promo, CU_TENSOR_MAP_FLOAT_OOB_FILL_NONE);
}

}

extern "C" void kernel_launch(void* const* d_in, const int* in_sizes, int n_in, void* d_out, int out_size) {
    (void)in_sizes; (void)n_in; (void)out_size;
    void* fn = nullptr;
    cudaDriverEntryPointQueryResult qr;
    cudaGetDriverEntryPoint("cuTensorMapEncodeTiled", &fn, cudaEnableDefault, &qr);
    EncodeFn enc = (EncodeFn)fn;
    Params p;
    make_map(enc, &p.mx, d_in[0], 2048, 512, 128, PROMO_X);
    make_map(enc, &p.mwA, d_in[1], 512, 1536, 64, PROMO_W);
    make_map(enc, &p.moA, d_in[2], 512, 512, 64, PROMO_W);
    make_map(enc, &p.mwB, d_in[4], 512, 1536, 64, PROMO_W);
    make_map(enc, &p.moB, d_in[5], 512, 512, 64, PROMO_W);
    p.gate_w = (const __nv_bfloat16*)d_in[6];
    p.out = (__nv_bfloat16*)d_out;
    cudaFuncSetAttribute(fused_kernel, cudaFuncAttributeMaxDynamicSharedMemorySize, SMEM_BYTES);
    fused_kernel<<<128, 384, SMEM_BYTES, cudaStreamPerThread>>>(p);
}
```

```cpp
#include <cuda_runtime.h>
#include <cuda_bf16.h>
#include <cuda.h>
#include <stdint.h>

namespace {

#define PACE0 (B_KDONE + 3)
#define PACE1 (B_KDONE + 5)
#define PACE2 (B_KDONE + 6)
#define PACE3 (B_KDONE + 6)
#define PACEB (B_KDONE + 14)
#define GDELAY 900
#define GTRIG 6
#define SDELAY 0
#define WOHOLD 8
#define EPRIOA 2
#define VW 1
#define TRICKLE 130
#define PP 7
#define PFIRST 1
#define INIT2 1
#define WOBAR (B_KVRDY + 1)
#define HACK 0
#define EPRIO 0
#define PFA (B_KDONE + 5)
#define PFB (B_KDONE + 8)
#define PROMO_X CU_TENSOR_MAP_L2_PROMOTION_L2_128B
#define PROMO_W CU_TENSOR_MAP_L2_PROMOTION_L2_128B
#define NPRE 1

constexpr uint32_t OFF_X = 0;
constexpr uint32_t OFF_KVOP = 9 * 16384, OFF_GATE = OFF_KVOP + 4096;
constexpr uint32_t OFF_PK = 13 * 16384;
constexpr uint32_t OFF_BAR = 14 * 16384;
constexpr uint32_t OFF_ONES = OFF_BAR + 1024;
constexpr uint32_t OFF_ZERO = OFF_ONES + 128;
constexpr uint32_t SMEM_BYTES = OFF_ZERO + 1024;
__host__ __device__ constexpr uint32_t off_stage(int rd) { return rd ? 12 * 16384 : 10 * 16384; }

constexpr int B_XFULL = 0;
constexpr int B_KFULL = 8;
constexpr int B_QFULL = 24;
constexpr int B_ZOK = 32;
constexpr int B_KVRDY = 33;
constexpr int B_OSTORED = 35;
constexpr int B_KDONE = 40;
constexpr int B_QDONE = 56;
constexpr int B_EDONE = 64;
constexpr int B_OSTEP = 66;
constexpr int B_OSTG = 68;
constexpr int B_ALLDONE = 79;
constexpr int B_OHALF = 70;
constexpr int B_CDONE = 72;
constexpr int B_CFULL = 80;

constexpr unsigned long long KV_BUF = 0xb8cbd89c9cba9cdbull, KV_PRE = 0x31489e24730c40ull;
constexpr uint32_t Q_BUF = 0xb89cb8a8u;
constexpr unsigned long long Q_PRE = 0x7bb4d2c080ull;
constexpr unsigned long long CHUNK_BUF = 0xd29a1b8c0d9ab8daull, CHUNK_PRE0 = 0x8c57039920ull, CHUNK_PRE1 = 0xb56b49ce40ull;

struct Params {
    CUtensorMap mx, mwA, mwB, moA, moB;
    const __nv_bfloat16* gate_w;
    __nv_bfloat16* out;
};

__device__ float4 g_kv[64 * 80];
__device__ uint4 g_obuf[16 * 16 * 1024];
__device__ unsigned g_zflag[8 * 32];
__device__ unsigned g_oflag[32 * 32];
__device__ uint2 g_gate[2048];
__device__ unsigned g_epoch;
#define STAMP(i) do {} while (0)
#define STAMPIF(i, cond) do {} while (0)
#define STAMP1(i) do {} while (0)
#define STAMPC(i, cond) do {} while (0)

__device__ __forceinline__ void mbar_init(uint32_t bar, uint32_t cnt) { asm volatile("mbarrier.init.shared::cta.b64 [%0], %1;" :: "r"(bar), "r"(cnt) : "memory"); }
__device__ __forceinline__ void mbar_expect_tx(uint32_t bar, uint32_t bytes) { asm volatile("mbarrier.arrive.expect_tx.shared::cta.b64 _, [%0], %1;" :: "r"(bar), "r"(bytes) : "memory"); }
__device__ __forceinline__ void mbar_arrive(uint32_t bar) { asm volatile("mbarrier.arrive.shared::cta.b64 _, [%0];" :: "r"(bar) : "memory"); }
__device__ __forceinline__ void mbar_wait_bounded(uint32_t bar) {
    asm volatile(
        "{\n .reg .pred p; .reg .u32 n;\n mov.u32 n, 0;\n"
        "W_LOOP:\n"
        " mbarrier.try_wait.parity.shared::cta.b64 p, [%0], 0;\n"
        " @p bra W_DONE;\n"
        " add.u32 n, n, 1;\n setp.lt.u32 p, n, 0x400000;\n @p bra W_LOOP;\n trap;\n"
        "W_DONE:\n}" :: "r"(bar) : "memory");
}
__device__ __forceinline__ void mbar_wait(uint32_t bar) {
    asm volatile("{\n .reg .pred p;\n W_LOOP:\n mbarrier.try_wait.parity.shared::cta.b64 p, [%0], 0;\n @!p bra W_LOOP;\n}" :: "r"(bar) : "memory");
}
__device__ __forceinline__ bool elect_one() {
    uint32_t p;
    asm volatile("{ .reg .pred P; elect.sync _|P, 0xffffffff; selp.u32 %0, 1, 0, P; }" : "=r"(p));
    return p;
}
__device__ __forceinline__ void tma_2d(uint32_t dst, const CUtensorMap* m, int c0, int c1, uint32_t bar) {
    asm volatile("cp.async.bulk.tensor.2d.shared::cluster.global.mbarrier::complete_tx::bytes [%0], [%1, {%3, %4}], [%2];"
        :: "r"(dst), "l"(m), "r"(bar), "r"(c0), "r"(c1) : "memory");
}
__device__ __forceinline__ void tma_prefetch_2d(const CUtensorMap* m, int c0, int c1) {
    asm volatile("cp.async.bulk.prefetch.tensor.2d.L2.global [%0, {%1, %2}];" :: "l"(m), "r"(c0), "r"(c1) : "memory");
}
__device__ __forceinline__ void bulk_load(uint32_t dst, const void* src, uint32_t bytes, uint32_t bar) {
    asm volatile("cp.async.bulk.shared::cluster.global.mbarrier::complete_tx::bytes [%0], [%1], %2, [%3];"
        :: "r"(dst), "l"(src), "r"(bytes), "r"(bar) : "memory");
}
__device__ __forceinline__ void bulk_store(void* dst, uint32_t src, uint32_t bytes) {
    asm volatile("cp.async.bulk.global.shared::cta.bulk_group [%0], [%1], %2;" :: "l"(dst), "r"(src), "r"(bytes) : "memory");
}
__device__ __forceinline__ void bulk_commit() { asm volatile("cp.async.bulk.commit_group;" ::: "memory"); }
__device__ __forceinline__ void bulk_wait_all() { asm volatile("cp.async.bulk.wait_group 0;" ::: "memory"); }
__device__ __forceinline__ void fence_async_smem() { asm volatile("fence.proxy.async.shared::cta;" ::: "memory"); }
__device__ __forceinline__ void fence_async_global() { asm volatile("fence.proxy.async.global;" ::: "memory"); }
__device__ __forceinline__ uint32_t clk32() { uint32_t c; asm volatile("mov.u32 %0, %%clock;" : "=r"(c) :: "memory"); return c; }
__device__ __forceinline__ void spin(uint32_t clks) { const uint32_t t0 = clk32(); while (clk32() - t0 < clks) {} }
__device__ __forceinline__ unsigned ld_relaxed(const unsigned* p) { unsigned v; asm volatile("ld.relaxed.gpu.global.u32 %0, [%1];" : "=r"(v) : "l"(p) : "memory"); return v; }
__device__ __forceinline__ void st_relaxed(unsigned* p, unsigned v) { asm volatile("st.relaxed.gpu.global.u32 [%0], %1;" :: "l"(p), "r"(v) : "memory"); }
__device__ __forceinline__ void red_add_v4(float4* p, float a, float b, float c, float d) {
    asm volatile("red.relaxed.gpu.global.add.v4.f32 [%0], {%1, %2, %3, %4};" :: "l"(p), "f"(a), "f"(b), "f"(c), "f"(d) : "memory");
}
__device__ __forceinline__ float4 ld_relaxed4(const float4* p) {
    float4 v;
    asm volatile("ld.relaxed.gpu.global.v4.f32 {%0, %1, %2, %3}, [%4];" : "=f"(v.x), "=f"(v.y), "=f"(v.z), "=f"(v.w) : "l"(p) : "memory");
    return v;
}
__device__ __forceinline__ void poll_eq(const unsigned* p, unsigned target) {
    int n = 0;
    while (!__all_sync(~0u, ld_relaxed(p) == target)) { if (++n > (1 << 21)) __trap(); }
}
__device__ __forceinline__ void nbar_sync(int id, int n) { asm volatile("bar.sync %0, %1;" :: "r"(id), "r"(n) : "memory"); }
__device__ __forceinline__ void nbar_arrive(int id, int n) { asm volatile("bar.arrive %0, %1;" :: "r"(id), "r"(n) : "memory"); }
__device__ __forceinline__ uint32_t pack_bf16(float lo, float hi) { uint32_t r; asm("cvt.rn.bf16x2.f32 %0, %1, %2;" : "=r"(r) : "f"(hi), "f"(lo)); return r; }
__device__ __forceinline__ float rcp_fast(float x) { float r; asm("rcp.approx.ftz.f32 %0, %1;" : "=f"(r) : "f"(x)); return r; }
__device__ __forceinline__ float ex2_fast(float x) { float r; asm("ex2.approx.ftz.f32 %0, %1;" : "=f"(r) : "f"(x)); return r; }
__device__ __forceinline__ void stmatrix_x4(uint32_t addr, uint32_t a, uint32_t b, uint32_t c, uint32_t d) {
    asm volatile("stmatrix.sync.aligned.m8n8.x4.shared.b16 [%0], {%1, %2, %3, %4};" :: "r"(addr), "r"(a), "r"(b), "r"(c), "r"(d) : "memory");
}
__device__ __forceinline__ void stmatrix_x4_t(uint32_t addr, uint32_t a, uint32_t b, uint32_t c, uint32_t d) {
    asm volatile("stmatrix.sync.aligned.m8n8.x4.trans.shared.b16 [%0], {%1, %2, %3, %4};" :: "r"(addr), "r"(a), "r"(b), "r"(c), "r"(d) : "memory");
}
__device__ __forceinline__ void sts32(uint32_t addr, uint32_t v) { asm volatile("st.shared.u32 [%0], %1;" :: "r"(addr), "r"(v) : "memory"); }
__device__ __forceinline__ void sts128(uint32_t addr, uint4 v) { asm volatile("st.shared.v4.u32 [%0], {%1, %2, %3, %4};" :: "r"(addr), "r"(v.x), "r"(v.y), "r"(v.z), "r"(v.w) : "memory"); }
__device__ __forceinline__ uint4 lds128(uint32_t addr) { uint4 v; asm volatile("ld.shared.v4.u32 {%0, %1, %2, %3}, [%4];" : "=r"(v.x), "=r"(v.y), "=r"(v.z), "=r"(v.w) : "r"(addr) : "memory"); return v; }
__device__ __forceinline__ uint32_t phi2(float t0, float t1) {
    float s0, s1;
    uint32_t m, r;
    asm("add.sat.f32 %0, %1, %2;" : "=f"(s0) : "f"(ex2_fast(t0 * 1.4426950408889634f)), "f"(1e-6f));
    asm("add.sat.f32 %0, %1, %2;" : "=f"(s1) : "f"(ex2_fast(t1 * 1.4426950408889634f)), "f"(1e-6f));
    asm("cvt.rn.relu.bf16x2.f32 %0, %1, %2;" : "=r"(m) : "f"(t1), "f"(t0));
    asm("add.rn.bf16x2 %0, %1, %2;" : "=r"(r) : "r"(pack_bf16(s0, s1)), "r"(m));
    return r;
}

__device__ __forceinline__ void wg_fence() { asm volatile("wgmma.fence.sync.aligned;" ::: "memory"); }
__device__ __forceinline__ void wg_commit() { asm volatile("wgmma.commit_group.sync.aligned;" ::: "memory"); }
template <int N> __device__ __forceinline__ void wg_wait() { asm volatile("wgmma.wait_group.sync.aligned %0;" :: "n"(N) : "memory"); }
__device__ __forceinline__ uint32_t desc_lo(uint32_t addr) { return (addr >> 4) | 0x10000u; }
#define ACC8(d, o) "+f"(d[o]), "+f"(d[o + 1]), "+f"(d[o + 2]), "+f"(d[o + 3]), "+f"(d[o + 4]), "+f"(d[o + 5]), "+f"(d[o + 6]), "+f"(d[o + 7])
template <int ACC>
__device__ __forceinline__ void wgmma_n128(float (&d)[64], uint32_t da, uint32_t db) {
    asm volatile("{ .reg .b64 a, b; mov.b64 a, {%64, 0x40000040}; mov.b64 b, {%65, 0x40000040};\n"
        "wgmma.mma_async.sync.aligned.m64n128k16.f32.bf16.bf16 "
        "{%0, %1, %2, %3, %4, %5, %6, %7, %8, %9, %10, %11, %12, %13, %14, %15, %16, %17, %18, %19, %20, %21, %22, %23, %24, %25, %26, %27, %28, %29, %30, %31, "
        "%32, %33, %34, %35, %36, %37, %38, %39, %40, %41, %42, %43, %44, %45, %46, %47, %48, %49, %50, %51, %52, %53, %54, %55, %56, %57, %58, %59, %60, %61, %62, %63}, "
        "a, b, %66, 1, 1, 1, 0; }"
        : ACC8(d, 0), ACC8(d, 8), ACC8(d, 16), ACC8(d, 24), ACC8(d, 32), ACC8(d, 40), ACC8(d, 48), ACC8(d, 56)
        : "r"(da), "r"(db), "n"(ACC));
}
template <int ACC>
__device__ __forceinline__ void wgmma_n64_rs(float (&d)[32], const uint32_t* a, uint32_t db) {
    asm volatile("{ .reg .b64 b; mov.b64 b, {%36, 0x40000040};\n"
        "wgmma.mma_async.sync.aligned.m64n64k16.f32.bf16.bf16 "
        "{%0, %1, %2, %3, %4, %5, %6, %7, %8, %9, %10, %11, %12, %13, %14, %15, %16, %17, %18, %19, %20, %21, %22, %23, %24, %25, %26, %27, %28, %29, %30, %31}, "
        "{%32, %33, %34, %35}, b, %37, 1, 1, 0; }"
        : ACC8(d, 0), ACC8(d, 8), ACC8(d, 16), ACC8(d, 24) : "r"(a[0]), "r"(a[1]), "r"(a[2]), "r"(a[3]), "r"(db), "n"(ACC));
}
template <int ACC>
__device__ __forceinline__ void wgmma_n8_rs(float (&d)[4], const uint32_t* a, uint32_t db) {
    asm volatile("{ .reg .b64 b; mov.b64 b, {%8, 0};\n"
        "wgmma.mma_async.sync.aligned.m64n8k16.f32.bf16.bf16 {%0, %1, %2, %3}, {%4, %5, %6, %7}, b, %9, 1, 1, 0; }"
        : "+f"(d[0]), "+f"(d[1]), "+f"(d[2]), "+f"(d[3]) : "r"(a[0]), "r"(a[1]), "r"(a[2]), "r"(a[3]), "r"(db), "n"(ACC));
}
__device__ __forceinline__ void wgmma_n24(float (&d)[12], uint32_t da, uint32_t db) {
    asm volatile("{ .reg .b64 a, b; mov.b64 a, {%12, 0x40000040}; mov.b64 b, {%13, 0x00000008};\n"
        "wgmma.mma_async.sync.aligned.m64n24k16.f32.bf16.bf16 {%0, %1, %2, %3, %4, %5, %6, %7, %8, %9, %10, %11}, a, b, 0, 1, 1, 1, 0; }"
        : ACC8(d, 0), "+f"(d[8]), "+f"(d[9]), "+f"(d[10]), "+f"(d[11]) : "r"(da), "r"(db));
}

template <int FIRST>
__device__ __forceinline__ void gemm_pair(float (&qa)[64], uint32_t da, uint32_t db) {
    wg_fence();
    wgmma_n128<!FIRST>(qa, da, db);
#pragma unroll
    for (int kk = 1; kk < 8; kk++) wgmma_n128<1>(qa, da + kk * 128, db + (kk >> 2) * 1024 + (kk & 3) * 2);
    wg_commit();
}

__global__ void __launch_bounds__(384, 1) fused_kernel(const __grid_constant__ Params p) {
    extern __shared__ __align__(1024) uint8_t smem_raw[];
    const uint32_t sb = (uint32_t)__cvta_generic_to_shared(smem_raw);
    const uint32_t bars = sb + OFF_BAR;
    const int pw = __shfl_sync(~0u, threadIdx.x >> 5, 0), warp = PFIRST ? (pw < 4 ? pw + 8 : pw - 4) : pw, lane = threadIdx.x & 31;
    const int grp = blockIdx.x >> 3, gi = blockIdx.x & 7;
    const int branch = grp >> 3, r = (grp & 7) * 2 + (gi & 1), cl = gi >> 1, c = branch * 4 + cl;
    STAMPIF(0, threadIdx.x == 0);
    const CUtensorMap* mw = branch ? &p.mwB : &p.mwA;

    if (warp == 8) {
        if (elect_one()) {
#pragma unroll
            for (int i = 0; i < (INIT2 ? 2 : 8); i++) mbar_init(bars + 8 * (B_XFULL + i), 1);
            if (INIT2) {
#pragma unroll
                for (int j = 0; j < 2; j++) {
                    mbar_expect_tx(bars + 8 * (B_XFULL + j), 16384);
                    tma_2d(sb + OFF_X + j * 16384, &p.mx, j * 64, r * 128, bars + 8 * (B_XFULL + j));
                }
#pragma unroll
                for (int i = 2; i < 8; i++) mbar_init(bars + 8 * (B_XFULL + i), 1);
            }
#pragma unroll 1
            for (int j = INIT2 ? 2 : 0; j < 8; j++) {
                mbar_expect_tx(bars + 8 * (B_XFULL + j), 16384);
                tma_2d(sb + OFF_X + j * 16384, &p.mx, j * 64, r * 128, bars + 8 * (B_XFULL + j));
                if (SDELAY && j == 1) spin(SDELAY);
            }
        }
    } else if (warp == 9) {
        if (elect_one()) {
#pragma unroll
            for (int i = 0; i < 8; i++) mbar_init(bars + 8 * (B_KFULL + i), 1);
            uint32_t tb = (uint32_t)KV_BUF;
#pragma unroll 1
            for (int j = 0; j < 5; j++) {
                const uint32_t bar = bars + 8 * (B_KFULL + j), dst = sb + (tb & 15) * 16384;
                mbar_expect_tx(bar, HACK & 2 ? 8192 : 16384);
                tma_2d(dst, mw, 512 + (j & 4) * 128 + cl * 128, (j & 3) * 128, bar);
                if (!(HACK & 2)) tma_2d(dst + 8192, mw, 512 + (j & 4) * 128 + cl * 128, (j & 3) * 128 + 64, bar);
                tb >>= 4;
                if (SDELAY && j == 0) spin(SDELAY);
            }
        }
    } else {
        if (warp == 0) sts32(sb + OFF_ONES + lane * 4, 0x3f803f80u);
        if (elect_one()) {
            const int bg = warp < 8 ? warp + 2 : warp;
            const uint32_t bar = bars + 64 * bg, cnt = bg < 5 || bg >= 10 ? 1 : 4;
            mbar_init(bar, bg == 4 ? 6 : bg >= 10 ? 5 : cnt);
#pragma unroll
            for (int i = 1; i < 8; i++) mbar_init(bar + 8 * i, cnt);
        }
        fence_async_smem();
    }
    __syncwarp();
    __syncthreads();

    if (warp < 8) {
        asm volatile("setmaxnreg.inc.sync.aligned.u32 208;");
        const int wq = warp & 3;
        const int g = lane >> 2, q = lane & 3;
        const uint32_t dx = desc_lo(sb + OFF_X);
        const uint32_t sw = ((lane >> 4) ^ (lane & 7)) << 4;
        const bool lead = elect_one();
        if (warp < 4) {
            uint32_t ktb = (uint32_t)KV_BUF;
            const uint32_t prow = sb + OFF_PK + (wq * 16 + (lane & 15)) * 128;
#pragma unroll 1
            for (int rd = 0; rd < 2; rd++) {
                float va[64];
                const uint32_t kb = bars + 64 * rd;
                float acc[64];
                mbar_wait(bars + 8 * B_XFULL);
                mbar_wait(bars + 8 * (B_XFULL + 1));
                mbar_wait(kb + 8 * B_KFULL);
                STAMP(30 + 8 * rd);
                gemm_pair<1>(acc, dx + (ktb & 15) * 1024, dx);
#pragma unroll 1
                for (int pr = 1; pr < 4; pr++) {
                    mbar_wait(bars + 8 * (B_XFULL + 2 * pr));
                    mbar_wait(bars + 8 * (B_XFULL + 2 * pr + 1));
                    mbar_wait(kb + 8 * (B_KFULL + pr));
                    STAMP(30 + 8 * rd + pr);
                    gemm_pair<0>(acc, dx + ((ktb >> (4 * pr)) & 15) * 1024, dx + pr * 2048);
                    wg_wait<1>();
                    if (lead) mbar_arrive(kb + 8 * (B_KDONE + pr - 1));
                }
                uint32_t pk[32];
                mbar_wait(kb + 8 * (B_KFULL + 4));
                STAMP(34 + 8 * rd);
                gemm_pair<1>(va, dx + ((ktb >> 16) & 15) * 1024, dx);
                wg_wait<1>();
                if (lead) mbar_arrive(kb + 8 * (B_KDONE + 3));
                nbar_sync(1, 128);
#define PHI_PART(I)                                                                              \
                _Pragma("unroll") for (int i = PP * I; i < (I == 3 ? 32 : PP * I + PP); i++) pk[i] = phi2(acc[2 * i], acc[2 * i + 1]); \
                _Pragma("unroll") for (int t = PP * I / 4; t < (I == 3 ? 8 : (PP * I + PP) / 4); t++)                     \
                    stmatrix_x4(prow + (t >> 2) * 8192 + (sw ^ ((t & 3) << 5)), pk[4 * t], pk[4 * t + 1], pk[4 * t + 2], pk[4 * t + 3]);
#define V_STEP(PR)                                                                               \
                mbar_wait(kb + 8 * (B_KFULL + 4 + PR));                                          \
                STAMP(34 + 8 * rd + PR);                                                         \
                gemm_pair<0>(va, dx + ((ktb >> (16 + 4 * PR)) & 15) * 1024, dx + PR * 2048);     \
                if (PR > VW) { PHI_PART(PR) }                                                    \
                wg_wait<1>();                                                                    \
                if (lead) mbar_arrive(kb + 8 * (B_KDONE + 3 + PR));                              \
                if (PR <= VW) { PHI_PART(PR) }
                PHI_PART(0) V_STEP(1) V_STEP(2) V_STEP(3)
                ktb = (uint32_t)(KV_BUF >> 32);
                float zz[4], e[32];
                wg_fence();
                wgmma_n8_rs<0>(zz, pk, (sb + OFF_ONES) >> 4);
#pragma unroll
                for (int t = 1; t < 8; t++) wgmma_n8_rs<1>(zz, pk + 4 * t, (sb + OFF_ONES) >> 4);
                wg_commit();
                fence_async_smem();
                nbar_sync(1, 128);
                mbar_wait(bars + 8 * B_ZOK);
                wg_wait<1>();
                if (lead) mbar_arrive(kb + 8 * (B_KDONE + 7));
                STAMP(2 + rd * 5);
                uint32_t vp[32];
#pragma unroll
                for (int i = 0; i < 32; i++) vp[i] = pack_bf16(va[2 * i], va[2 * i + 1]);
                const uint32_t dp = desc_lo(sb + OFF_PK);
                wg_fence();
                wgmma_n64_rs<0>(e, vp, dp);
#pragma unroll
                for (int t = 1; t < 8; t++) wgmma_n64_rs<1>(e, vp + 4 * t, dp + (t >> 2) * 512 + (t & 3) * 2);
                wg_commit();
                STAMP(3 + rd * 5);
                nbar_arrive(4, 256);
                wg_wait<0>();
                STAMP(4 + rd * 5);
                float kv[8];
#pragma unroll
                for (int i = 0; i < 8; i++) kv[i] = wq & 2 ? (wq & 1 ? e[24 + i] : e[16 + i]) : (wq & 1 ? e[8 + i] : e[i]);
                float4* kvp = g_kv + (c * 8 + rd * 4 + wq) * 80;
                red_add_v4(kvp + lane, kv[0], kv[1], kv[2], q & 1 ? 1.f : kv[3]);
                red_add_v4(kvp + 32 + lane, kv[4], kv[5], kv[6], q & 1 ? 1.f : kv[7]);
                asm volatile("{ .reg .pred p; setp.ne.u32 p, %5, 0; @p red.relaxed.gpu.global.add.v4.f32 [%0], {%1, %2, %3, %4}; }"
                             :: "l"(kvp + 64 + (lane >> 1)), "f"(kv[3]), "f"(kv[7]), "f"(q & 2 ? zz[2] : zz[0]), "f"(1.f), "r"(q & 1) : "memory");
                if (lead) mbar_arrive(bars + 8 * (B_EDONE + rd));
                STAMP(5 + rd * 5);
            }
            float oacc[64];
#pragma unroll
            for (int i = 0; i < 64; i++) oacc[i] = 0.f;
            unsigned long long tbl = CHUNK_BUF;
            nbar_sync(2, 256);
#pragma unroll 1
            for (int n = 0; n < 16; n++) {
                if (n == NPRE) {
                    wg_wait<0>();
                    if (NPRE > 0 && lead) mbar_arrive(bars + 8 * (B_CDONE + NPRE - 1));
                    mbar_wait(bars + 8 * B_OSTORED);
                }
                mbar_wait(bars + 8 * (B_CFULL + n));
                STAMPIF(11, n == 0); STAMPIF(12, n == 1); STAMPIF(13, n == NPRE); STAMPIF(14, n == 8); STAMPIF(15, n == 9);
                const uint32_t db = dx + ((uint32_t)tbl & 15) * 1024, dw = dx + n * 512;
                tbl >>= 4;
                wg_fence();
#pragma unroll
                for (int kk = 0; kk < 4; kk++) wgmma_n128<1>(oacc, dw + kk * 128, db + kk * 2);
                wg_commit();
                if (n < 8) {
                    wg_wait<1>();
                    if (n > 0 && n != NPRE && lead) mbar_arrive(bars + 8 * (B_CDONE + n - 1));
                }
            }
            wg_wait<0>();
            STAMP(16);
            const uint32_t stg = sb + OFF_X + 49152 + wq * 4096;
#pragma unroll
            for (int j = 0; j < 8; j++) {
                const int row = 16 * j + (lane & 7) + ((lane >> 4) << 3);
                stmatrix_x4_t(stg + row * 32 + ((((lane >> 3) ^ (lane >> 2)) & 1) << 4),
                              pack_bf16(oacc[8 * j], oacc[8 * j + 1]), pack_bf16(oacc[8 * j + 2], oacc[8 * j + 3]),
                              pack_bf16(oacc[8 * j + 4], oacc[8 * j + 5]), pack_bf16(oacc[8 * j + 6], oacc[8 * j + 7]));
            }
            __syncwarp();
            uint4* op = reinterpret_cast<uint4*>(p.out + (r * 128 + (lane >> 1)) * 512 + c * 64 + wq * 16) + (lane & 1);
#pragma unroll
            for (int j = 0; j < 8; j++) op[j * 1024] = lds128(stg + j * 512 + (lane >> 1) * 32 + (((lane ^ (lane >> 3)) & 1) << 4));
            STAMP(17);
            if (lead) mbar_arrive(bars + 8 * B_ALLDONE);
        } else {
            {
                const unsigned tgt = ld_relaxed(&g_epoch) + 1;
                const int f = g & 1;
                const uint4 w0 = __ldg(reinterpret_cast<const uint4*>(p.gate_w) + 2 * lane + f), w1 = __ldg(reinterpret_cast<const uint4*>(p.gate_w) + 2 * lane + 1 - f);
                const uint32_t wr[8] = {w0.x, w0.y, w0.z, w0.w, w1.x, w1.y, w1.z, w1.w};
                const uint32_t xa = sb + OFF_X + g * 16384 + c * 2048 + wq * 512, ch = (2 * q + f) ^ ((wq & 1) << 2);
#pragma unroll 1
                for (int j = 0; j < 8; j++) mbar_wait(bars + 8 * (B_XFULL + j));
                float a[4] = {0.f, 0.f, 0.f, 0.f};
#pragma unroll
                for (int u = 0; u < 4; u++) {
                    const uint32_t ad = xa + u * 128 + ((ch ^ u) << 4);
                    const uint4 x0 = lds128(ad), x1 = lds128(ad ^ 16);
                    const uint32_t x[8] = {x0.x, x0.y, x0.z, x0.w, x1.x, x1.y, x1.z, x1.w};
#pragma unroll
                    for (int k = 0; k < 8; k++) {
                        a[u] = fmaf(__uint_as_float(x[k] << 16), __uint_as_float(wr[k] << 16), a[u]);
                        a[u] = fmaf(__uint_as_float(x[k] & 0xffff0000u), __uint_as_float(wr[k] & 0xffff0000u), a[u]);
                    }
                }
                const float t0 = (lane & 16 ? a[2] : a[0]) + __shfl_xor_sync(~0u, lane & 16 ? a[0] : a[2], 16);
                const float t1 = (lane & 16 ? a[3] : a[1]) + __shfl_xor_sync(~0u, lane & 16 ? a[1] : a[3], 16);
                float t = (lane & 8 ? t1 : t0) + __shfl_xor_sync(~0u, lane & 8 ? t0 : t1, 8);
#pragma unroll
                for (int s = 4; s >= 1; s >>= 1) t += __shfl_xor_sync(~0u, t, s);
                if ((lane & 7) == 0)
                    asm volatile("st.relaxed.gpu.global.v2.b32 [%0], {%1, %2};" :: "l"(g_gate + r * 128 + c * 16 + wq * 4 + (lane >> 3)), "r"(__float_as_uint(t)), "r"(tgt) : "memory");
                if (lead) mbar_arrive(bars + 8 * B_ZOK);
            }
            uint32_t qtb = Q_BUF;
            float gt[4];
#pragma unroll 1
            for (int rd = 0; rd < 2; rd++) {
                float acc[64];
                const uint32_t qb = bars + 32 * rd;
                mbar_wait(bars + 8 * (rd ? PACEB : PACE0));
                mbar_wait(qb + 8 * B_QFULL);
                if (rd && EPRIO == 0) nbar_sync(4, 256);
                STAMP(18 + rd * 6);
                STAMP(46 + 4 * rd);
                gemm_pair<1>(acc, dx + (qtb & 15) * 1024, dx);
#pragma unroll 1
                for (int pr = 1; pr < 4; pr++) {
                    const bool paced = rd == 0 && pr < 3;
                    if (paced) { wg_wait<0>(); if (lead) mbar_arrive(qb + 8 * (B_QDONE + pr - 1)); }
                    mbar_wait(bars + 8 * (pr == 1 ? PACE1 : pr == 2 ? PACE2 : PACE3));
                    mbar_wait(qb + 8 * (B_QFULL + pr));
                    if (pr == (rd ? EPRIO : EPRIOA)) nbar_sync(4, 256);
                    qtb >>= 4;
                    STAMP(46 + 4 * rd + pr);
                    gemm_pair<0>(acc, dx + (qtb & 15) * 1024, dx + pr * 2048);
                    if (rd && pr == 3) nbar_arrive(2, 256);
                    wg_wait<1>();
                    if (!paced && lead) mbar_arrive(qb + 8 * (B_QDONE + pr - 1));
                }
                qtb >>= 4;
                wg_wait<0>();
                if (lead) mbar_arrive(qb + 8 * (B_QDONE + 3));
                STAMP(19 + rd * 6);
                const uint32_t stg = sb + off_stage(rd);
                const uint32_t srow = stg + (wq * 16 + (lane & 15)) * 128;
#pragma unroll
                for (int t = 0; t < 8; t++)
                    stmatrix_x4(srow + (t >> 2) * 8192 + (sw ^ ((t & 3) << 5)),
                                phi2(acc[8 * t], acc[8 * t + 1]), phi2(acc[8 * t + 2], acc[8 * t + 3]),
                                phi2(acc[8 * t + 4], acc[8 * t + 5]), phi2(acc[8 * t + 6], acc[8 * t + 7]));
                fence_async_smem();
                nbar_sync(3, 128);
                STAMP(20 + rd * 6);
                mbar_wait(bars + 8 * (B_KVRDY + rd));
                STAMP(21 + rd * 6);
                if (rd == 0) {
#pragma unroll
                    for (int i = 0; i < 4; i++)
                        asm volatile("ld.shared.f32 %0, [%1];" : "=f"(gt[i]) : "r"(sb + OFF_GATE + 4 * ((i >> 1) * 64 + wq * 16 + (i & 1) * 8 + g)));
                }
                float o[8][12];
                const uint32_t dp = desc_lo(stg), dk = ((sb + OFF_KVOP) >> 4) | (24u << 16);
                wg_fence();
#pragma unroll
                for (int i = 0; i < 8; i++) wgmma_n24(o[i], dp + (i >> 2) * 512 + (i & 3) * 128, dk + (i & 3) * 48);
                wg_commit();
                wg_wait<0>();
                if (lead) mbar_arrive(bars + 8 * (B_OSTEP + rd));
                nbar_sync(3, 128);
                STAMP(22 + rd * 6);
#pragma unroll
                for (int i = 0; i < 8; i++) {
                    if (i == 4) {
                        fence_async_smem();
                        __syncwarp();
                        if (lead) mbar_arrive(bars + 8 * (B_OHALF + rd));
                    }
                    const float slo = gt[2 * (i >> 2)] * rcp_fast(o[i][8] + 1e-6f), shi = gt[2 * (i >> 2) + 1] * rcp_fast(o[i][10] + 1e-6f);
                    stmatrix_x4(srow + (i >> 2) * 8192 + (sw ^ ((i & 3) << 5)),
                                pack_bf16(o[i][0] * slo, o[i][1] * slo), pack_bf16(o[i][2] * shi, o[i][3] * shi),
                                pack_bf16(o[i][4] * slo, o[i][5] * slo), pack_bf16(o[i][6] * shi, o[i][7] * shi));
                }
                fence_async_smem();
                __syncwarp();
                if (lead) { mbar_arrive(bars + 8 * (B_OSTG + rd)); mbar_arrive(bars + 8 * (B_CFULL + 8 * rd)); }
                STAMP(23 + rd * 6);
            }
        }
    } else {
        asm volatile("setmaxnreg.dec.sync.aligned.u32 88;");
        if (warp == 8) {
            if (elect_one()) {
#pragma unroll 1
                for (int i = 0; i < 8; i++) {
                    if (i) mbar_wait(bars + 8 * (B_KDONE + ((uint32_t)(Q_PRE >> (5 * i)) & 31)));
                    const uint32_t bar = bars + 8 * (B_QFULL + i), dst = sb + ((Q_BUF >> (4 * i)) & 15) * 16384;
                    mbar_expect_tx(bar, HACK & 2 ? 8192 : 16384);
                    tma_2d(dst, mw, cl * 128 + (i >> 2) * 64, (i & 3) * 128, bar);
                    if (!(HACK & 2)) tma_2d(dst + 8192, mw, cl * 128 + (i >> 2) * 64, (i & 3) * 128 + 64, bar);
                }
#pragma unroll 1
                for (int n = 0; n < 16; n++) {
                    if ((n & 3) == 0) mbar_wait(bars + 8 * (B_QDONE + 4 + (n >> 2)));
                    if (n == WOHOLD) mbar_wait(bars + 8 * WOBAR);
                    const int m = n & 7, cc = m == 0 ? c : (m - 1 < c ? m - 1 : m);
                    STAMPC(60, n == 15);
                    if (!(HACK & 4)) tma_2d(sb + OFF_X + n * 8192, cc >= 4 ? &p.moB : &p.moA, c * 64, (cc & 3) * 128 + (n >> 3) * 64, bars + 8 * (B_CFULL + n));
                }
            }
        } else {
            const unsigned tgt = ld_relaxed(&g_epoch) + 1;
            if (tgt == 0) __trap();
            if (warp == 9) {
                if (elect_one()) {
#pragma unroll 1
                    for (int j = 5; j < 16; j++) {
                        mbar_wait(bars + 8 * (B_KDONE + ((uint32_t)(KV_PRE >> (5 * j - 25)) & 31)));
                        const uint32_t bar = bars + 8 * (B_KFULL + j), dst = sb + ((uint32_t)(KV_BUF >> (4 * j)) & 15) * 16384;
                        mbar_expect_tx(bar, HACK & 2 ? 8192 : 16384);
                        tma_2d(dst, mw, 512 + (j & 4) * 128 + cl * 128 + (j >> 3) * 64, (j & 3) * 128, bar);
                        if (!(HACK & 2)) tma_2d(dst + 8192, mw, 512 + (j & 4) * 128 + cl * 128 + (j >> 3) * 64, (j & 3) * 128 + 64, bar);
                    }
#pragma unroll 1
                    for (int n = 0; n < 16; n++) mbar_expect_tx(bars + 8 * (B_CFULL + n), n & 7 ? (HACK & 1 ? 8192 : 16384) + (HACK & 4 ? 0 : 8192) : (HACK & 4 ? 0 : 8192));
                }
            } else if (warp == 10) {
                const bool lead = elect_one();
                if (r == 0) {
                    sts128(sb + OFF_ZERO + lane * 16, make_uint4(0, 0, 0, 0));
                    sts128(sb + OFF_ZERO + 512 + lane * 16, make_uint4(0, 0, 0, 0));
                    fence_async_smem();
                    __syncwarp();
                    if (elect_one()) {
#pragma unroll 1
                        for (int i = 0; i < 10; i++) bulk_store(g_kv + c * 640 + i * 64, sb + OFF_ZERO, 1024);
                        bulk_commit();
                        bulk_wait_all();
                        st_relaxed(g_zflag + c * 32, tgt);
                    }
                    __syncwarp();
                }
                poll_eq(g_zflag + c * 32, tgt);
                if (lead) mbar_arrive(bars + 8 * B_ZOK);
#pragma unroll 1
                for (int rd = 0; rd < 2; rd++) {
                    mbar_wait(bars + 8 * (B_EDONE + rd));
                    if (rd) mbar_wait(bars + 8 * (B_QDONE + GTRIG)); else spin(GDELAY);
                    const float4* kvp = g_kv + (c * 8 + rd * 4) * 80;
                    const bool odd = lane & 1;
                    const uint4* gp = reinterpret_cast<const uint4*>(g_gate + r * 128) + lane * 2;
                    float4 v[12];
                    uint4 ga, gb;
                    int n = 0;
                    while (true) {
                        bool ok = true;
                        asm volatile("ld.relaxed.gpu.global.v2.b64 {%0, %1}, [%2];" : "=l"(*(unsigned long long*)&ga.x), "=l"(*(unsigned long long*)&ga.z) : "l"(gp) : "memory");
                        asm volatile("ld.relaxed.gpu.global.v2.b64 {%0, %1}, [%2];" : "=l"(*(unsigned long long*)&gb.x), "=l"(*(unsigned long long*)&gb.z) : "l"(gp + 1) : "memory");
#pragma unroll
                        for (int h = 0; h < 4; h++) {
                            v[3 * h] = ld_relaxed4(kvp + h * 80 + lane);
                            v[3 * h + 1] = ld_relaxed4(kvp + h * 80 + 32 + lane);
                            v[3 * h + 2] = ld_relaxed4(kvp + h * 80 + 64 + (lane >> 1));
                        }
#pragma unroll
                        for (int i = 0; i < 12; i++) ok = ok && v[i].w == 16.f;
                        if (__all_sync(~0u, (ok || !odd) && ga.y == tgt && ga.w == tgt && gb.y == tgt && gb.w == tgt)) break;
                        if (++n > (1 << 20)) __trap();
                    }
                    STAMP(54 + rd);
                    mbar_wait(bars + 8 * (rd ? B_QDONE + 5 : B_KDONE + 9));
                    if (rd == 0) {
                        const float sg = branch ? 1.4426950408889634f : -1.4426950408889634f;
                        ga.x = __float_as_uint(rcp_fast(1.f + ex2_fast(__uint_as_float(ga.x) * sg)));
                        ga.y = __float_as_uint(rcp_fast(1.f + ex2_fast(__uint_as_float(ga.z) * sg)));
                        ga.z = __float_as_uint(rcp_fast(1.f + ex2_fast(__uint_as_float(gb.x) * sg)));
                        ga.w = __float_as_uint(rcp_fast(1.f + ex2_fast(__uint_as_float(gb.z) * sg)));
                        sts128(sb + OFF_GATE + lane * 16, ga);
                    }
                    const uint32_t dst = sb + OFF_KVOP + (lane >> 4) * 384 + (lane & 15) * 16;
#pragma unroll
                    for (int h = 0; h < 4; h++) {
                        const float4 a = v[3 * h], b = v[3 * h + 1], d = v[3 * h + 2];
                        stmatrix_x4(dst + h * 768, pack_bf16(a.x, a.y), pack_bf16(a.z, odd ? d.x : a.w), pack_bf16(b.x, b.y), pack_bf16(b.z, odd ? d.y : b.w));
                    }
                    stmatrix_x4_t(sb + OFF_KVOP + 256 + (lane >> 3) * 768 + ((lane >> 2) & 1) * 384 + (lane & 3) * 32,
                                  pack_bf16(v[2].z, v[2].z), pack_bf16(v[5].z, v[5].z), pack_bf16(v[8].z, v[8].z), pack_bf16(v[11].z, v[11].z));
                    fence_async_smem();
                    __syncwarp();
                    if (lead) mbar_arrive(bars + 8 * (B_KVRDY + rd));
                }
            } else {
                if (elect_one()) {
                    mbar_arrive(bars + 8 * B_ZOK);
                    if (PFA) {
                        mbar_wait(bars + 8 * PFA);
                        tma_prefetch_2d(mw, 512 + (r >> 3) * 512 + cl * 128 + 64, (r & 7) * 64);
                    }
                    if (PFB) {
                        mbar_wait(bars + 8 * PFB);
                        if (r < 8) tma_prefetch_2d(mw, cl * 128 + 64, r * 64);
                        tma_prefetch_2d(r < 8 ? &p.moA : &p.moB, c * 64, (r & 7) * 64);
                    }
#pragma unroll 1
                    for (int rd = 0; rd < 2; rd++) {
                        mbar_wait(bars + 8 * (B_OHALF + rd));
#pragma unroll 1
                        for (int i = 0; i < 8; i += rd ? 4 : 1) {
                            if (i == 4) mbar_wait(bars + 8 * (B_OSTG + rd));
                            bulk_store(g_obuf + ((r * 2 + rd) * 8 + c) * 1024 + i * 128, sb + off_stage(rd) + i * 2048, rd ? 8192 : 2048);
                            if (!rd) spin(TRICKLE);
                        }
                        bulk_commit();
                        bulk_wait_all();
                        st_relaxed(g_oflag + (r * 2 + rd) * 32 + c, tgt);
                        STAMP1(58 + rd);
                    }
                    mbar_arrive(bars + 8 * B_OSTORED);
                    mbar_wait_bounded(bars + 8 * B_ALLDONE);
                }
            }
            if (warp < 11) {
                __syncwarp();
                const int hf = warp - 9;
                const uint32_t tb = (uint32_t)(CHUNK_BUF >> (32 * hf));
                const unsigned long long tp = hf ? CHUNK_PRE1 : CHUNK_PRE0;
                const unsigned* fp = g_oflag + (r * 2 + hf) * 32 + (lane & 7);
                if (hf) mbar_wait(bars + 8 * (B_OSTG + 1));
                unsigned v0 = ld_relaxed(fp);
                spin(300);
                int m = 1;
                for (int n = 0; m < 8; n++) {
                    const unsigned v1 = ld_relaxed(fp);
                    const unsigned rdy = __ballot_sync(~0u, v0 == tgt);
                    v0 = v1;
                    unsigned ok = ((rdy & ((1u << c) - 1)) << 1) | (rdy & (0xfeu << c) & 0xffu);
                    if (!((rdy >> c) & 1)) ok &= ~16u;
                    const int m1 = __ffs(~ok >> m) - 1 + m;
                    if (m1 > m) {
                        STAMPIF(56 + hf, m == 1);
                        if (elect_one()) {
                            fence_async_global();
#pragma unroll 1
                            for (; m < m1; m++) {
                                mbar_wait(bars + 8 * (B_QDONE + ((uint32_t)(tp >> (5 * m)) & 31)));
                                bulk_load(sb + ((tb >> (4 * m)) & 15) * 16384, g_obuf + ((r * 2 + hf) * 8 + (m - 1 < c ? m - 1 : m)) * 1024, HACK & 1 ? 8192 : 16384,
                                          bars + 8 * (B_CFULL + hf * 8 + m));
                            }
                        }
                        __syncwarp();
                        m = m1;
                    }
                    if (n > (1 << 20)) __trap();
                }
                if (blockIdx.x == 0 && hf && lane == 0) st_relaxed(&g_epoch, tgt);
            }
        }
    }
}

typedef CUresult (*EncodeFn)(CUtensorMap*, CUtensorMapDataType, cuuint32_t, void*, const cuuint64_t*, const cuuint64_t*,
                             const cuuint32_t*, const cuuint32_t*, CUtensorMapInterleave, CUtensorMapSwizzle,
                             CUtensorMapL2promotion, CUtensorMapFloatOOBfill);

void make_map(EncodeFn enc, CUtensorMap* m, const void* ptr, uint64_t rows, uint64_t cols, uint32_t box_rows, CUtensorMapL2promotion promo) {
    cuuint64_t gd[2] = {cols, rows}, gs[1] = {cols * 2};
    cuuint32_t bd[2] = {64, box_rows}, es[2] = {1, 1};
    enc(m, CU_TENSOR_MAP_DATA_TYPE_BFLOAT16, 2, const_cast<void*>(ptr), gd, gs, bd, es, CU_TENSOR_MAP_INTERLEAVE_NONE,
        CU_TENSOR_MAP_SWIZZLE_128B, promo, CU_TENSOR_MAP_FLOAT_OOB_FILL_NONE);
}

}

extern "C" void kernel_launch(void* const* d_in, const int* in_sizes, int n_in, void* d_out, int out_size) {
    (void)in_sizes; (void)n_in; (void)out_size;
    void* fn = nullptr;
    cudaDriverEntryPointQueryResult qr;
    cudaGetDriverEntryPoint("cuTensorMapEncodeTiled", &fn, cudaEnableDefault, &qr);
    EncodeFn enc = (EncodeFn)fn;
    Params p;
    make_map(enc, &p.mx, d_in[0], 2048, 512, 128, PROMO_X);
    make_map(enc, &p.mwA, d_in[1], 512, 1536, 64, PROMO_W);
    make_map(enc, &p.moA, d_in[2], 512, 512, 64, PROMO_W);
    make_map(enc, &p.mwB, d_in[4], 512, 1536, 64, PROMO_W);
    make_map(enc, &p.moB, d_in[5], 512, 512, 64, PROMO_W);
    p.gate_w = (const __nv_bfloat16*)d_in[6];
    p.out = (__nv_bfloat16*)d_out;
    cudaFuncSetAttribute(fused_kernel, cudaFuncAttributeMaxDynamicSharedMemorySize, SMEM_BYTES);
    fused_kernel<<<128, 384, SMEM_BYTES, cudaStreamPerThread>>>(p);
}
```
